```python
import torch

def _softmax(x, axis=-1):
    return torch.softmax(x, dim=axis)
def _gelu(x):
    return torch.nn.functional.gelu(x, approximate="tanh")
def _silu(x):
    return torch.nn.functional.silu(x)
def _sigmoid(x):
    return torch.sigmoid(x)
def _layernorm(x, axis=-1, eps=1e-5):
    m = x.mean(dim=axis, keepdim=True)
    v = x.var(dim=axis, keepdim=True, unbiased=False)
    return (x - m) / torch.sqrt(v + eps)
def _scatter_add(tgt, idx, src, axis=0):
    return tgt.clone().index_add_(axis, idx, src)
def _segment_sum(src, seg, n):
    out = torch.zeros((n,) + src.shape[1:], dtype=src.dtype)
    return out.index_add_(0, seg, src)
def _pad(x, pw):
    flat = tuple(v for pair in reversed(pw) for v in pair)
    return torch.nn.functional.pad(x, flat)

kernel_name = 'interleave_layers__sliding_local_dilated__mixer_s_mlp__prompt'

def setup_inputs():

    _w = (lambda a: (lambda t: t.to(torch.bfloat16) if t.is_floating_point() else t)(torch.as_tensor(a)))
    def _A_setup():
        B, S, D = 1, 2048, 512
        return {
            "x": _w((lambda *s: torch.randn(*s, dtype=torch.bfloat16) * 0.05)(B, S, D)),
            "wqkv": _w((lambda *s: torch.randn(*s, dtype=torch.bfloat16) * 0.1)(D, 3 * D)),
            "wo": _w((lambda *s: torch.randn(*s, dtype=torch.bfloat16) * 0.1)(D, D)),
        }
    _A_in = _A_setup()

    def _B_setup():
        B, S, D, F = 1, 2048, 512, 1792
        return {
            "x":  _w((lambda *s: torch.randn(*s, dtype=torch.bfloat16) * 0.05)(B, S, D)),
            "w1": _w((lambda *s: torch.randn(*s, dtype=torch.bfloat16) * 3.2)(D, D) * (D ** -0.5)),
            "w2": _w((lambda *s: torch.randn(*s, dtype=torch.bfloat16) * 3.2)(D, D) * (D ** -0.5)),
            "w3": _w((lambda *s: torch.randn(*s, dtype=torch.bfloat16) * 3.2)(D, F) * (D ** -0.5)),
            "w4": _w((lambda *s: torch.randn(*s, dtype=torch.bfloat16) * 3.2)(F, D) * (F ** -0.5)),
        }
    _B_in = _B_setup()

    return {
        "A_x": _A_in["x"],
        "A_wqkv": _A_in["wqkv"],
        "A_wo": _A_in["wo"],
        "B_x": _B_in["x"],
        "B_w1": _B_in["w1"],
        "B_w2": _B_in["w2"],
        "B_w3": _B_in["w3"],
        "B_w4": _B_in["w4"],
    }

def reference(A_x, A_wqkv, A_wo, B_x, B_w1, B_w2, B_w3, B_w4):
    def _A_ref(x, wqkv, wo):
        B, S, D = x.shape
        H = 32; Dh = D // H
        W, dil = 8, 2
        qkv = (lambda x, *d: x.permute(*d))((x @ wqkv).reshape(B, S, 3, H, Dh), 2, 0, 3, 1, 4)
        q, k, v = qkv[0], qkv[1], qkv[2]
        scale = Dh ** -0.5
        pos = torch.arange(S)
        off = torch.arange(W) * dil
        idx = pos[:, None] - off[None, :]
        mask = idx >= 0
        idx_c = torch.where(mask, idx, 0).reshape(-1)
        kg = k[:, :, idx_c, :].reshape(B, H, S, W, Dh)
        vg = v[:, :, idx_c, :].reshape(B, H, S, W, Dh)
        logits = torch.einsum("bhsd,bhswd->bhsw", q, kg) * scale
        logits = torch.where(mask[None, None, :, :], logits, -1e9)
        attn = _softmax(logits, axis=-1)
        o = torch.einsum("bhsw,bhswd->bhsd", attn, vg)
        return (lambda x, *d: x.permute(*d))(o, 0, 2, 1, 3).reshape(B, S, D) @ wo

    def _B_ref(x, w1, w2, w3, w4):
        B, S, D = x.shape
        h = _gelu(_layernorm(x, axis=-1) @ w1)
        c = D // 4
        g0 = _pad(h[:, :, 0*c:1*c], ((0, 0), (1, 0), (0, 0)))[:, :S, :]
        g1 = _pad(h[:, :, 1*c:2*c], ((0, 0), (0, 1), (0, 0)))[:, 1:, :]
        g2 = _pad(h[:, :, 2*c:3*c], ((0, 0), (2, 0), (0, 0)))[:, :S, :]
        g3 = _pad(h[:, :, 3*c:   ], ((0, 0), (0, 2), (0, 0)))[:, 2:, :]
        hs = torch.concatenate([g0, g1, g2, g3], axis=-1) @ w2
        x1 = x + hs
        h2 = _gelu(_layernorm(x1, axis=-1) @ w3) @ w4
        return x1 + h2

    x = A_x
    x = x + _A_ref(_layernorm(x, axis=-1), A_wqkv, A_wo)
    x = x + _B_ref(_layernorm(x, axis=-1), B_w1, B_w2, B_w3, B_w4)
    x = x + _A_ref(_layernorm(x, axis=-1), A_wqkv, A_wo)
    x = x + _B_ref(_layernorm(x, axis=-1), B_w1, B_w2, B_w3, B_w4)
    return x
```

```cpp
#include <cuda_runtime.h>
#include <cuda_bf16.h>
#include <cuda.h>
#include <stdint.h>
#include <mma.h>

namespace mk {
constexpr int SEQ = 2048, DM = 512, FF = 1792;
constexpr int NCL = 15, CS = 8;
constexpr int SLOT_B = 18432, HALF_B = 9216;
constexpr int NWS = 9, WS_B = 8192;
constexpr int OFF_W = 8 * SLOT_B;
constexpr int OFF_SP = OFF_W + NWS * WS_B;
constexpr int OFF_MU = OFF_SP + 9216;
constexpr int OFF_RS = OFF_MU + 576;
constexpr int OFF_RR = OFF_RS + 576;
constexpr int OFF_BAR = OFF_RR + 576;
constexpr int B_FULL = OFF_BAR, B_WFULL = B_FULL + 64, B_WEMPTY = B_WFULL + 72, B_SFREE = B_WEMPTY + 72,
              B_STAGED = B_SFREE + 8, B_STAGED2 = B_STAGED + 8, B_SBAR = B_STAGED2 + 8, B_SREADY = B_SBAR + 8,
              B_HALO = B_SREADY + 8, B_SFREE2 = B_HALO + 8, B_RXF = B_SFREE2 + 8, B_PBAR = B_RXF + 8,
              B_HALO2 = B_PBAR + 8,
              OFF_CONST = B_HALO2 + 8;
constexpr int SMEM_BYTES = 232448;
static_assert(OFF_CONST + 4 <= SMEM_BYTES, "smem");
static_assert(B_PBAR == B_FULL + 8 * 34 && B_SFREE == B_FULL + 8 * 26 && B_SFREE2 == B_FULL + 8 * 32, "barrier table");
constexpr int QP_B = 80 * 128, KP_B = 88 * 128;
constexpr int MC_DELAY = 215;
constexpr uint32_t SPIN_LIMIT = 1u << 20;
constexpr float LN_EPS = 1e-5f;

struct Params {
  alignas(64) CUtensorMap tx;
  alignas(64) CUtensorMap tqkv;
  alignas(64) CUtensorMap two;
  alignas(64) CUtensorMap tw1;
  alignas(64) CUtensorMap tw2;
  alignas(64) CUtensorMap tw3;
  alignas(64) CUtensorMap tw4;
  __nv_bfloat16* out;
};

__device__ __align__(1024) unsigned char g_bounce[NCL * 2 * CS * SLOT_B];
__device__ __align__(1024) unsigned char g_h3[NCL * CS * 4 * SLOT_B];
__device__ __align__(128) unsigned long long g_llkv[2 * NCL * CS * 1024];
__device__ __align__(128) unsigned long long g_llh[2 * NCL * CS * 2 * 32];
__device__ unsigned int g_epoch[NCL * CS];

__device__ __forceinline__ uint32_t smem_u32(const void* p) { return (uint32_t)__cvta_generic_to_shared(p); }
__device__ __forceinline__ void mbar_init(uint32_t bar, uint32_t cnt) {
  asm volatile("mbarrier.init.shared::cta.b64 [%0], %1;" ::"r"(bar), "r"(cnt) : "memory");
}
__device__ __forceinline__ void mbar_expect_tx(uint32_t bar, uint32_t bytes) {
  asm volatile("mbarrier.arrive.expect_tx.shared::cta.b64 _, [%0], %1;" ::"r"(bar), "r"(bytes) : "memory");
}
__device__ __forceinline__ void mbar_arrive(uint32_t bar) {
  asm volatile("mbarrier.arrive.shared::cta.b64 _, [%0];" ::"r"(bar) : "memory");
}
__device__ __forceinline__ void mbar_arrive_n(uint32_t bar, uint32_t n) {
  asm volatile("mbarrier.arrive.shared::cta.b64 _, [%0], %1;" ::"r"(bar), "r"(n) : "memory");
}
__device__ __forceinline__ uint32_t mapa(uint32_t addr, uint32_t rank) {
  uint32_t r;
  asm("mapa.shared::cluster.u32 %0, %1, %2;" : "=r"(r) : "r"(addr), "r"(rank));
  return r;
}
__device__ __forceinline__ void mbar_arrive_remote(uint32_t bar, uint32_t rank, uint32_t n) {
  asm volatile("mbarrier.arrive.shared::cluster.b64 _, [%0], %1;" ::"r"(mapa(bar, rank)), "r"(n) : "memory");
}
__device__ __forceinline__ uint32_t mbar_try(uint32_t bar, uint32_t par) {
  uint32_t ok;
  asm volatile("{\n.reg .pred p;\nmbarrier.try_wait.parity.shared::cta.b64 p, [%1], %2;\nselp.u32 %0, 1, 0, p;\n}"
               : "=r"(ok) : "r"(bar), "r"(par) : "memory");
  return ok;
}
__device__ __forceinline__ uint32_t mbar_test(uint32_t bar, uint32_t par) {
  uint32_t ok;
  asm volatile("{\n.reg .pred p;\nmbarrier.test_wait.parity.shared::cta.b64 p, [%1], %2;\nselp.u32 %0, 1, 0, p;\n}"
               : "=r"(ok) : "r"(bar), "r"(par) : "memory");
  return ok;
}
__device__ __forceinline__ void mbar_wait(uint32_t bar, uint32_t par) {
  uint32_t it = 0;
  while (!mbar_try(bar, par)) {
    if (++it > SPIN_LIMIT) __trap();
  }
}
__device__ __forceinline__ bool elect_one() {
  uint32_t p;
  asm volatile("{\n.reg .pred P;\nelect.sync _|P, 0xffffffff;\nselp.u32 %0, 1, 0, P;\n}" : "=r"(p));
  return p != 0;
}
__device__ __forceinline__ int uniform(int v) { return __shfl_sync(0xffffffffu, v, 0); }
__device__ __forceinline__ void fence_async_smem() { asm volatile("fence.proxy.async.shared::cta;" ::: "memory"); }
__device__ __forceinline__ void fence_async_global() { asm volatile("fence.proxy.async.global;" ::: "memory"); }
__device__ __forceinline__ void bar_sync(int id, int n) { asm volatile("bar.sync %0, %1;" ::"r"(id), "r"(n) : "memory"); }
__device__ __forceinline__ void tma2d(uint32_t dst, const CUtensorMap* m, int x, int y, uint32_t bar) {
  asm volatile("cp.async.bulk.tensor.2d.shared::cluster.global.mbarrier::complete_tx::bytes [%0], [%1, {%2, %3}], [%4];"
               ::"r"(dst), "l"(m), "r"(x), "r"(y), "r"(bar) : "memory");
}
__device__ __forceinline__ void tma2d_mc(uint32_t dst, const CUtensorMap* m, int x, int y, uint32_t bar, uint16_t mask) {
  asm volatile(
      "cp.async.bulk.tensor.2d.shared::cluster.global.mbarrier::complete_tx::bytes.multicast::cluster [%0], [%1, {%2, %3}], [%4], %5;"
      ::"r"(dst), "l"(m), "r"(x), "r"(y), "r"(bar), "h"(mask) : "memory");
}
__device__ __forceinline__ void bulk_store(void* dst, uint32_t src, uint32_t bytes) {
  asm volatile("cp.async.bulk.global.shared::cta.bulk_group [%0], [%1], %2;" ::"l"(dst), "r"(src), "r"(bytes) : "memory");
}
__device__ __forceinline__ void bulk_load_mc(uint32_t dst, const void* src, uint32_t bytes, uint32_t bar, uint16_t mask) {
  asm volatile(
      "cp.async.bulk.shared::cluster.global.mbarrier::complete_tx::bytes.multicast::cluster [%0], [%1], %2, [%3], %4;"
      ::"r"(dst), "l"(src), "r"(bytes), "r"(bar), "h"(mask) : "memory");
}
__device__ __forceinline__ void bulk_commit() { asm volatile("cp.async.bulk.commit_group;" ::: "memory"); }
__device__ __forceinline__ void bulk_wait_all() { asm volatile("cp.async.bulk.wait_group 0;" ::: "memory"); }
__device__ __forceinline__ void bulk_wait_read_all() { asm volatile("cp.async.bulk.wait_group.read 0;" ::: "memory"); }
__device__ __forceinline__ void cluster_arrive() { asm volatile("barrier.cluster.arrive.release;" ::: "memory"); }
__device__ __forceinline__ void cluster_wait() { asm volatile("barrier.cluster.wait.acquire;" ::: "memory"); }
__device__ __forceinline__ void wg_fence() { asm volatile("wgmma.fence.sync.aligned;" ::: "memory"); }
__device__ __forceinline__ void wg_commit() { asm volatile("wgmma.commit_group.sync.aligned;" ::: "memory"); }
template <int N>
__device__ __forceinline__ void wg_wait() { asm volatile("wgmma.wait_group.sync.aligned %0;" ::"n"(N) : "memory"); }

__device__ __forceinline__ void stsm4t(uint32_t a, uint32_t r0, uint32_t r1, uint32_t r2, uint32_t r3) {
  asm volatile("stmatrix.sync.aligned.m8n8.x4.trans.shared.b16 [%0], {%1, %2, %3, %4};" ::"r"(a), "r"(r0), "r"(r1), "r"(r2), "r"(r3) : "memory");
}
__device__ __forceinline__ void stsm2t(uint32_t a, uint32_t r0, uint32_t r1) {
  asm volatile("stmatrix.sync.aligned.m8n8.x2.trans.shared.b16 [%0], {%1, %2};" ::"r"(a), "r"(r0), "r"(r1) : "memory");
}
__device__ __forceinline__ void stsm4(uint32_t a, uint32_t r0, uint32_t r1, uint32_t r2, uint32_t r3) {
  asm volatile("stmatrix.sync.aligned.m8n8.x4.shared.b16 [%0], {%1, %2, %3, %4};" ::"r"(a), "r"(r0), "r"(r1), "r"(r2), "r"(r3) : "memory");
}
__device__ __forceinline__ void ldsm4(uint32_t a, uint32_t& r0, uint32_t& r1, uint32_t& r2, uint32_t& r3) {
  asm volatile("ldmatrix.sync.aligned.m8n8.x4.shared.b16 {%0, %1, %2, %3}, [%4];" : "=r"(r0), "=r"(r1), "=r"(r2), "=r"(r3) : "r"(a) : "memory");
}
__device__ __forceinline__ void ldsm2(uint32_t a, uint32_t& r0, uint32_t& r1) {
  asm volatile("ldmatrix.sync.aligned.m8n8.x2.shared.b16 {%0, %1}, [%2];" : "=r"(r0), "=r"(r1) : "r"(a) : "memory");
}
__device__ __forceinline__ void ldsm4t(uint32_t a, uint32_t& r0, uint32_t& r1, uint32_t& r2, uint32_t& r3) {
  asm volatile("ldmatrix.sync.aligned.m8n8.x4.trans.shared.b16 {%0, %1, %2, %3}, [%4];" : "=r"(r0), "=r"(r1), "=r"(r2), "=r"(r3) : "r"(a) : "memory");
}
__device__ __forceinline__ void ldsm2t(uint32_t a, uint32_t& r0, uint32_t& r1) {
  asm volatile("ldmatrix.sync.aligned.m8n8.x2.trans.shared.b16 {%0, %1}, [%2];" : "=r"(r0), "=r"(r1) : "r"(a) : "memory");
}
__device__ __forceinline__ void mma16816(float (&d)[4], uint32_t a0, uint32_t a1, uint32_t a2, uint32_t a3, uint32_t b0, uint32_t b1) {
  asm volatile("mma.sync.aligned.m16n8k16.row.col.f32.bf16.bf16.f32 {%0, %1, %2, %3}, {%4, %5, %6, %7}, {%8, %9}, {%0, %1, %2, %3};"
               : "+f"(d[0]), "+f"(d[1]), "+f"(d[2]), "+f"(d[3]) : "r"(a0), "r"(a1), "r"(a2), "r"(a3), "r"(b0), "r"(b1));
}
__device__ __forceinline__ void mma1688(float (&d)[4], uint32_t a0, uint32_t a1, uint32_t b0) {
  asm volatile("mma.sync.aligned.m16n8k8.row.col.f32.bf16.bf16.f32 {%0, %1, %2, %3}, {%4, %5}, {%6}, {%0, %1, %2, %3};"
               : "+f"(d[0]), "+f"(d[1]), "+f"(d[2]), "+f"(d[3]) : "r"(a0), "r"(a1), "r"(b0));
}
__device__ __forceinline__ float4 lds128f(uint32_t a) {
  float4 v;
  asm volatile("ld.shared.v4.f32 {%0, %1, %2, %3}, [%4];" : "=f"(v.x), "=f"(v.y), "=f"(v.z), "=f"(v.w) : "r"(a) : "memory");
  return v;
}
__device__ __forceinline__ uint4 lds128u(uint32_t a) {
  uint4 v;
  asm volatile("ld.shared.v4.u32 {%0, %1, %2, %3}, [%4];" : "=r"(v.x), "=r"(v.y), "=r"(v.z), "=r"(v.w) : "r"(a) : "memory");
  return v;
}
__device__ __forceinline__ float2 lds64f(uint32_t a) {
  float2 v;
  asm volatile("ld.shared.v2.f32 {%0, %1}, [%2];" : "=f"(v.x), "=f"(v.y) : "r"(a) : "memory");
  return v;
}
__device__ __forceinline__ void sts128u(uint32_t a, uint32_t x, uint32_t y, uint32_t z, uint32_t w) {
  asm volatile("st.shared.v4.u32 [%0], {%1, %2, %3, %4};" ::"r"(a), "r"(x), "r"(y), "r"(z), "r"(w) : "memory");
}
__device__ __forceinline__ void sts64f(uint32_t a, float x, float y) {
  asm volatile("st.shared.v2.f32 [%0], {%1, %2};" ::"r"(a), "f"(x), "f"(y) : "memory");
}
__device__ __forceinline__ void sts32f(uint32_t a, float x) { asm volatile("st.shared.f32 [%0], %1;" ::"r"(a), "f"(x) : "memory"); }
__device__ __forceinline__ void sts16(uint32_t a, uint32_t x) {
  asm volatile("st.shared.u16 [%0], %1;" ::"r"(a), "h"((unsigned short)x) : "memory");
}
__device__ __forceinline__ void bulk_s2s(uint32_t dst, uint32_t src, uint32_t bytes, uint32_t bar) {
  asm volatile("cp.async.bulk.shared::cluster.shared::cta.mbarrier::complete_tx::bytes [%0], [%1], %2, [%3];"
               ::"r"(dst), "r"(src), "r"(bytes), "r"(bar) : "memory");
}
__device__ __forceinline__ void bar_arrive(int id, int n) { asm volatile("bar.arrive %0, %1;" ::"r"(id), "r"(n) : "memory"); }
__device__ __forceinline__ void ll_store(unsigned long long* p, uint32_t data, uint32_t tag) {
  unsigned long long v = ((unsigned long long)tag << 32) | data;
  asm volatile("st.relaxed.gpu.global.b64 [%0], %1;" ::"l"(p), "l"(v) : "memory");
}
__device__ __forceinline__ unsigned long long ll_load(const unsigned long long* p) {
  unsigned long long v;
  asm volatile("ld.relaxed.gpu.global.b64 %0, [%1];" : "=l"(v) : "l"(p) : "memory");
  return v;
}
__device__ __forceinline__ uint32_t pack_bf16(float lo, float hi) {
  uint32_t r;
  asm("cvt.rn.bf16x2.f32 %0, %1, %2;" : "=r"(r) : "f"(hi), "f"(lo));
  return r;
}
__device__ __forceinline__ float bf_lo(uint32_t v) { return __uint_as_float(v << 16); }
__device__ __forceinline__ float bf_hi(uint32_t v) { return __uint_as_float(v & 0xFFFF0000u); }
__device__ __forceinline__ float gelu_half(float h) {
  const float k0 = 2.f * 0.7978845608028654f, k1 = 8.f * 0.7978845608028654f * 0.044715f;
  float u = h * fmaf(h * h, k1, k0);
  float t;
  asm("tanh.approx.f32 %0, %1;" : "=f"(t) : "f"(u));
  return fmaf(h, t, h);
}
__device__ __forceinline__ float ex2(float x) {
  float y;
  asm("ex2.approx.ftz.f32 %0, %1;" : "=f"(y) : "f"(x));
  return y;
}

__device__ __forceinline__ void staged_arrive(uint32_t bar, int lane) {
  __syncwarp();
  if (lane == 0) mbar_arrive(bar);
}

__device__ __forceinline__ void wgmma_n72(float (&d)[36], uint64_t da, uint64_t db, int scale_d) {
  asm volatile("{\n.reg .pred p;\nsetp.ne.b32 p, %38, 0;\n"
    "wgmma.mma_async.sync.aligned.m64n72k16.f32.bf16.bf16 "
    "{%0, %1, %2, %3, %4, %5, %6, %7, %8, %9, %10, %11, "
    "%12, %13, %14, %15, %16, %17, %18, %19, %20, %21, %22, %23, "
    "%24, %25, %26, %27, %28, %29, %30, %31, %32, %33, %34, %35}, "
    "%36, %37, p, 1, 1, 1, 0;\n}\n"
    : "+f"(d[0]), "+f"(d[1]), "+f"(d[2]), "+f"(d[3]), "+f"(d[4]), "+f"(d[5]), "+f"(d[6]), "+f"(d[7]),
      "+f"(d[8]), "+f"(d[9]), "+f"(d[10]), "+f"(d[11]), "+f"(d[12]), "+f"(d[13]), "+f"(d[14]), "+f"(d[15]),
      "+f"(d[16]), "+f"(d[17]), "+f"(d[18]), "+f"(d[19]), "+f"(d[20]), "+f"(d[21]), "+f"(d[22]), "+f"(d[23]),
      "+f"(d[24]), "+f"(d[25]), "+f"(d[26]), "+f"(d[27]), "+f"(d[28]), "+f"(d[29]), "+f"(d[30]), "+f"(d[31]),
      "+f"(d[32]), "+f"(d[33]), "+f"(d[34]), "+f"(d[35])
    : "l"(da), "l"(db), "r"(scale_d));
}
__device__ __forceinline__ void wgmma_n144(float (&d)[72], uint64_t da, uint64_t db, int scale_d) {
  asm volatile("{\n.reg .pred p;\nsetp.ne.b32 p, %74, 0;\n"
    "wgmma.mma_async.sync.aligned.m64n144k16.f32.bf16.bf16 "
    "{%0, %1, %2, %3, %4, %5, %6, %7, %8, %9, %10, %11, "
    "%12, %13, %14, %15, %16, %17, %18, %19, %20, %21, %22, %23, "
    "%24, %25, %26, %27, %28, %29, %30, %31, %32, %33, %34, %35, "
    "%36, %37, %38, %39, %40, %41, %42, %43, %44, %45, %46, %47, "
    "%48, %49, %50, %51, %52, %53, %54, %55, %56, %57, %58, %59, "
    "%60, %61, %62, %63, %64, %65, %66, %67, %68, %69, %70, %71}, "
    "%72, %73, p, 1, 1, 1, 0;\n}\n"
    : "+f"(d[0]), "+f"(d[1]), "+f"(d[2]), "+f"(d[3]), "+f"(d[4]), "+f"(d[5]), "+f"(d[6]), "+f"(d[7]),
      "+f"(d[8]), "+f"(d[9]), "+f"(d[10]), "+f"(d[11]), "+f"(d[12]), "+f"(d[13]), "+f"(d[14]), "+f"(d[15]),
      "+f"(d[16]), "+f"(d[17]), "+f"(d[18]), "+f"(d[19]), "+f"(d[20]), "+f"(d[21]), "+f"(d[22]), "+f"(d[23]),
      "+f"(d[24]), "+f"(d[25]), "+f"(d[26]), "+f"(d[27]), "+f"(d[28]), "+f"(d[29]), "+f"(d[30]), "+f"(d[31]),
      "+f"(d[32]), "+f"(d[33]), "+f"(d[34]), "+f"(d[35]), "+f"(d[36]), "+f"(d[37]), "+f"(d[38]), "+f"(d[39]),
      "+f"(d[40]), "+f"(d[41]), "+f"(d[42]), "+f"(d[43]), "+f"(d[44]), "+f"(d[45]), "+f"(d[46]), "+f"(d[47]),
      "+f"(d[48]), "+f"(d[49]), "+f"(d[50]), "+f"(d[51]), "+f"(d[52]), "+f"(d[53]), "+f"(d[54]), "+f"(d[55]),
      "+f"(d[56]), "+f"(d[57]), "+f"(d[58]), "+f"(d[59]), "+f"(d[60]), "+f"(d[61]), "+f"(d[62]), "+f"(d[63]),
      "+f"(d[64]), "+f"(d[65]), "+f"(d[66]), "+f"(d[67]), "+f"(d[68]), "+f"(d[69]), "+f"(d[70]), "+f"(d[71])
    : "l"(da), "l"(db), "r"(scale_d));
}
__device__ __forceinline__ void wgmma_n72_tb(float (&d)[36], uint64_t da, uint64_t db, int scale_d) {
  asm volatile("{\n.reg .pred p;\nsetp.ne.b32 p, %38, 0;\n"
    "wgmma.mma_async.sync.aligned.m64n72k16.f32.bf16.bf16 "
    "{%0, %1, %2, %3, %4, %5, %6, %7, %8, %9, %10, %11, "
    "%12, %13, %14, %15, %16, %17, %18, %19, %20, %21, %22, %23, "
    "%24, %25, %26, %27, %28, %29, %30, %31, %32, %33, %34, %35}, "
    "%36, %37, p, 1, 1, 1, 1;\n}\n"
    : "+f"(d[0]), "+f"(d[1]), "+f"(d[2]), "+f"(d[3]), "+f"(d[4]), "+f"(d[5]), "+f"(d[6]), "+f"(d[7]),
      "+f"(d[8]), "+f"(d[9]), "+f"(d[10]), "+f"(d[11]), "+f"(d[12]), "+f"(d[13]), "+f"(d[14]), "+f"(d[15]),
      "+f"(d[16]), "+f"(d[17]), "+f"(d[18]), "+f"(d[19]), "+f"(d[20]), "+f"(d[21]), "+f"(d[22]), "+f"(d[23]),
      "+f"(d[24]), "+f"(d[25]), "+f"(d[26]), "+f"(d[27]), "+f"(d[28]), "+f"(d[29]), "+f"(d[30]), "+f"(d[31]),
      "+f"(d[32]), "+f"(d[33]), "+f"(d[34]), "+f"(d[35])
    : "l"(da), "l"(db), "r"(scale_d));
}

constexpr uint64_t DESC_HI = ((uint64_t)(64u | (1u << 30))) << 32;
__device__ __forceinline__ uint64_t desc_a(uint32_t addr) { return DESC_HI | (uint64_t)(((addr & 0x3FFFFu) >> 4) | (64u << 16)); }
__device__ __forceinline__ uint64_t desc_b(uint32_t addr) { return DESC_HI | (uint64_t)(((addr & 0x3FFFFu) >> 4) | (1u << 16)); }
__device__ __forceinline__ uint64_t desc_of(uint32_t lo) { return DESC_HI | (uint64_t)lo; }

struct Ctx {
  uint32_t sb;
  int r, cl;
  int s, w, lane;
  int nA, nB, tokA;
  int el;
};

__device__ __forceinline__ int opaque(int v) { int o; asm volatile("mov.b32 %0, %1;" : "=r"(o) : "r"(v)); return o; }
__device__ __forceinline__ Ctx fresh(const Ctx& a) {
  Ctx b = a;
  b.sb = (uint32_t)opaque((int)a.sb); b.r = opaque(a.r); b.w = opaque(a.w); b.lane = opaque(a.lane);
  b.nA = opaque(a.nA); b.nB = opaque(a.nB);
  return b;
}

__device__ __forceinline__ int shift_of(int j) { return (j < 2) ? 1 : (j < 4) ? -1 : (j < 6) ? 2 : -2; }
__device__ __forceinline__ uint32_t hfill_off(int j) { int d = shift_of(j); return d > 0 ? 128u * d : 0u; }
__device__ __forceinline__ uint32_t hfill_len(int j, int nB) {
  int d = shift_of(j);
  return d > 0 ? (uint32_t)(SLOT_B - 128 * d) : (uint32_t)(128 * (72 + nB + d));
}

template <int M>
__device__ __forceinline__ void fence_acc(float (&acc)[M]) {
#pragma unroll
  for (int i = 0; i < M; i++) asm volatile("" : "+f"(acc[i])::"memory");
}

template <int N>
__device__ __forceinline__ void wgmma_k16(float (&acc)[N / 2], uint64_t da, uint64_t db, int scale_d) {
  if constexpr (N == 72) wgmma_n72(acc, da, db, scale_d);
  else wgmma_n144(acc, da, db, scale_d);
}

template <int N>
__device__ __forceinline__ void mma_tile(float (&acc)[N / 2], const Ctx& cx, uint32_t b_off, int g0, uint32_t fpar, uint32_t wcnt,
                                         bool fresh_slot, int stride, int wait_bar, int arrive_bar) {
  int slot = g0 % NWS;
  uint32_t par = (g0 / NWS) & 1;
  if (N == 144) {
#pragma unroll
    for (int i = 0; i < N / 2; i++) acc[i] = 0.f;
  }
  const uint32_t wb = (uint32_t)opaque((int)desc_a(cx.sb + OFF_W)), ab = (uint32_t)opaque((int)desc_b(cx.sb + b_off));
  mbar_wait(cx.sb + B_FULL + 8 * cx.r, fpar);
  if (fresh_slot) fence_async_smem();
  mbar_wait(cx.sb + B_WFULL + 8 * slot, par);
  int j = cx.r, pslot = 0;
#pragma unroll
  for (int i = 0; i < 8; i++) {
    const uint64_t da = desc_of(wb + slot * (WS_B >> 4)), db = desc_of(ab + j * (SLOT_B >> 4));
    const int nj = (i + (i >= cx.r ? 1 : 0)) & 7;
    const int nslot = slot + stride >= NWS ? slot + stride - NWS : slot + stride;
    const uint32_t npar = par ^ (nslot < slot ? 1u : 0u);
    const uint32_t fb = cx.sb + B_FULL + 8 * nj, wf = cx.sb + B_WFULL + 8 * nslot;
    uint32_t ok0 = 1, ok1 = 1;
    if (N == 144 && i == 1 && wait_bar) bar_sync(wait_bar, 256);

    wg_fence();
    wgmma_k16<N>(acc, da, db, N == 72 || i > 0);
    if (i < 7) ok0 = mbar_test(fb, fpar);
    wgmma_k16<N>(acc, da + 128, db + 2, 1);
    if (i < 7) ok1 = mbar_test(wf, npar);
    wgmma_k16<N>(acc, da + 256, db + 4, 1);
    wgmma_k16<N>(acc, da + 384, db + 6, 1);
    wg_commit();
    if (i > 0) {
      wg_wait<1>();
      if (cx.el) mbar_arrive_n(cx.sb + B_WEMPTY + 8 * pslot, wcnt);
    }
    if (i < 7 && __builtin_expect(!(ok0 & ok1), 0)) {
      mbar_wait(fb, fpar);
      mbar_wait(wf, npar);
    }
    pslot = slot; slot = nslot; par = npar; j = nj;
  }

  if (N == 144 && arrive_bar) bar_arrive(arrive_bar, 256);
  wg_wait<0>();
  fence_acc(acc);

  if (cx.el) mbar_arrive_n(cx.sb + B_WEMPTY + 8 * pslot, wcnt);
}

constexpr uint64_t DESC_H_HI = ((uint64_t)8u) << 32;
__device__ __forceinline__ uint32_t desc_h_lo(uint32_t addr) { return ((addr & 0x3FFFFu) >> 4) | (72u << 16); }
__device__ __forceinline__ void wgmma4_h(float (&acc)[36], uint64_t da, uint32_t blo) {
  const uint64_t db = DESC_H_HI | (uint64_t)blo;
  wgmma_n72_tb(acc, da, db, 1);
  wgmma_n72_tb(acc, da + 128, db + 144, 1);
  wgmma_n72_tb(acc, da + 256, db + 288, 1);
  wgmma_n72_tb(acc, da + 384, db + 432, 1);
}
__device__ __forceinline__ void wgmma4_h_probe(float (&acc)[36], uint64_t da, uint32_t blo, uint32_t bar0, uint32_t par0,
                                               uint32_t bar1, uint32_t par1, uint32_t& ok0, uint32_t& ok1) {
  const uint64_t db = DESC_H_HI | (uint64_t)blo;
  wgmma_n72_tb(acc, da, db, 1);
  ok0 = mbar_test(bar0, par0);
  wgmma_n72_tb(acc, da + 128, db + 144, 1);
  ok1 = mbar_test(bar1, par1);
  wgmma_n72_tb(acc, da + 256, db + 288, 1);
  wgmma_n72_tb(acc, da + 384, db + 432, 1);
}
__device__ __forceinline__ void global_arrive(uint32_t bar, int lane) {
  __syncwarp();
  if (lane == 0) mbar_arrive(bar);
}
__device__ __forceinline__ void fence_gpu() { asm volatile("fence.acq_rel.gpu;" ::: "memory"); }

__device__ __forceinline__ void mma_w4(float (&own)[36], const Ctx& cx, int g0, int fidx, int L) {
  float frn[36];

  int slot = g0 % NWS;
  uint32_t par = (g0 / NWS) & 1;
#pragma unroll
  for (int i = 0; i < 36; i++) frn[i] = 0.f;
  const uint32_t wb = (uint32_t)opaque((int)desc_a(cx.sb + OFF_W)), ab = (uint32_t)opaque((int)desc_h_lo(cx.sb + cx.s * HALF_B));
  const int gbase = cx.r & 4;
  const uint32_t fpa = fidx & 1;
  {
    int ps1 = 0, i = 0;
    mbar_wait(cx.sb + B_FULL, fpa);
    global_arrive(cx.sb + B_STAGED2, cx.lane);
    mbar_wait(cx.sb + B_WFULL + 8 * slot, par);

#pragma unroll 1
    do {
      const int s1 = slot + 1 == NWS ? 0 : slot + 1, s2 = s1 + 1 == NWS ? 0 : s1 + 1;
      const uint32_t p1 = par ^ (s1 == 0 ? 1u : 0u), p2 = p1 ^ (s2 == 0 ? 1u : 0u);
      const uint32_t blo = ab + i * (SLOT_B >> 4);
      const uint32_t w1 = cx.sb + B_WFULL + 8 * s1, w2 = cx.sb + B_WFULL + 8 * s2, fn = cx.sb + B_FULL + 8 * ((i + 1) & 7);
      uint32_t ok0, ok1;
      wg_fence();
      wgmma4_h_probe(own, desc_of(wb + slot * (WS_B >> 4)), blo, w1, p1, w1, p1, ok0, ok1);
      wg_commit();
      if (i > 0) {
        wg_wait<1>();
        if (cx.el) {
          mbar_arrive(cx.sb + B_WEMPTY + 8 * ps1);
          mbar_arrive_remote(cx.sb + (i <= 4 ? B_SFREE : B_SFREE2), gbase + ((i - 1) & 3), i <= 4 ? 2 : 1);
        }
      }
      if (__builtin_expect(!ok1, 0)) mbar_wait(w1, p1);
      wg_fence();
      wgmma4_h_probe(frn, desc_of(wb + s1 * (WS_B >> 4)), blo, fn, fpa, w2, p2, ok0, ok1);
      wg_commit();
      wg_wait<1>();
      if (cx.el) mbar_arrive(cx.sb + B_WEMPTY + 8 * slot);
      if (__builtin_expect(!(ok0 & ok1), 0)) {
        if (i < 7) mbar_wait(fn, fpa);
        mbar_wait(w2, p2);
      }
      ps1 = s1; slot = s2; par = p2;
    } while (++i < 8);
    wg_wait<0>();
    if (cx.el) {
      mbar_arrive(cx.sb + B_WEMPTY + 8 * ps1);
      mbar_arrive_remote(cx.sb + B_SFREE2, gbase + 3, 1);
      mbar_arrive_remote(cx.sb + B_RXF, cx.r ^ 4, 1);
    }
  }

  int psb = 0;
  {
    int c = 0;
    mbar_wait(cx.sb + B_FULL, fpa ^ 1);
#pragma unroll 1
    do {
      const int j0 = c < 4 ? c : 4 + cx.s, j1 = c < 4 ? c + 1 : 6 + cx.s;
      const int s1 = slot + 1 == NWS ? 0 : slot + 1, s2 = s1 + 1 == NWS ? 0 : s1 + 1;
      const uint32_t p1 = par ^ (s1 == 0 ? 1u : 0u), p2 = p1 ^ (s2 == 0 ? 1u : 0u);
      const int j2 = (c + 2 < 4 ? c + 2 : 4 + cx.s) & 7;
      const uint32_t f1 = cx.sb + B_FULL + 8 * j1, f2 = cx.sb + B_FULL + 8 * j2;
      const uint32_t w1 = cx.sb + B_WFULL + 8 * s1, w2 = cx.sb + B_WFULL + 8 * s2;
      uint32_t ok0, ok1;
      wg_fence();
      wgmma4_h_probe(frn, desc_of(wb + slot * (WS_B >> 4)), ab + j0 * (SLOT_B >> 4), f1, fpa ^ 1, w1, p1, ok0, ok1);
      wg_commit();
      if (c > 0) {
        wg_wait<1>();
        if (cx.el) mbar_arrive(cx.sb + B_WEMPTY + 8 * psb);
      }
      if (__builtin_expect(!(ok0 & ok1), 0)) { mbar_wait(f1, fpa ^ 1); mbar_wait(w1, p1); }
      if (c >= 4) mbar_wait(f1 ^ 8, fpa ^ 1);
      wg_fence();
      wgmma4_h_probe(frn, desc_of(wb + s1 * (WS_B >> 4)), ab + j1 * (SLOT_B >> 4), f2, fpa ^ 1, w2, p2, ok0, ok1);
      wg_commit();
      wg_wait<1>();
      if (cx.el) mbar_arrive(cx.sb + B_WEMPTY + 8 * slot);
      if (__builtin_expect(!(ok0 & ok1), 0)) { mbar_wait(f2, fpa ^ 1); mbar_wait(w2, p2); }
      if (c == 2) mbar_wait(f2 ^ 8, fpa ^ 1);
      psb = s1; slot = s2; par = p2;
      c += 2;
    } while (c < 6);
  }

  {
    const int s1 = slot + 1 == NWS ? 0 : slot + 1;
    const uint32_t p1 = par ^ (s1 == 0 ? 1u : 0u);
    mbar_wait(cx.sb + B_WFULL + 8 * slot, par);
    wg_fence();
    wgmma4_h(own, desc_of(wb + slot * (WS_B >> 4)), ab);
    wg_commit();
    wg_wait<1>();
    fence_acc(frn);
    if (cx.el) mbar_arrive(cx.sb + B_WEMPTY + 8 * psb);
    const int t = cx.w * 32 + cx.lane;
    const uint32_t snd = cx.sb + (5 - cx.s + ((cx.r == 5 - cx.s) ? 2 : 0)) * SLOT_B + cx.s * HALF_B;
#pragma unroll
    for (int q = 0; q < 4; q++)
      sts128u(snd + (q * 128 + t) * 16, pack_bf16(frn[8 * q], frn[8 * q + 1]), pack_bf16(frn[8 * q + 2], frn[8 * q + 3]),
              pack_bf16(frn[8 * q + 4], frn[8 * q + 5]), pack_bf16(frn[8 * q + 6], frn[8 * q + 7]));
    asm volatile("st.shared.v2.u32 [%0], {%1, %2};" ::"r"(snd + 8192 + t * 8), "r"(pack_bf16(frn[32], frn[33])),
                 "r"(pack_bf16(frn[34], frn[35])) : "memory");
    bar_arrive(10 + cx.s, 160);
    psb = slot; slot = s1; par = p1;
  }

  {
    int c = 1;
#pragma unroll 1
    do {
      const int j = c < 4 ? c : 2 * c - 4 + cx.s;
      mbar_wait(cx.sb + B_WFULL + 8 * slot, par);
      wg_fence();
      wgmma4_h(own, desc_of(wb + slot * (WS_B >> 4)), ab + j * (SLOT_B >> 4));
      wg_commit();
      wg_wait<1>();
      if (cx.el) mbar_arrive(cx.sb + B_WEMPTY + 8 * psb);
      psb = slot;
      if (++slot == NWS) { slot = 0; par ^= 1; }
    } while (++c < 6);
    wg_wait<0>();
    fence_acc(own);
    if (cx.el) mbar_arrive(cx.sb + B_WEMPTY + 8 * psb);
  }

  {
    mbar_wait(cx.sb + B_PBAR, L & 1);

    const int t = cx.w * 32 + cx.lane;
    const uint32_t rcv = cx.sb + (7 - cx.s - ((cx.r == 5 - cx.s) ? 2 : 0)) * SLOT_B + cx.s * HALF_B;
#pragma unroll
    for (int q = 0; q < 4; q++) {
      const uint4 v = lds128u(rcv + (q * 128 + t) * 16);
      own[8 * q + 0] += bf_lo(v.x); own[8 * q + 1] += bf_hi(v.x); own[8 * q + 2] += bf_lo(v.y); own[8 * q + 3] += bf_hi(v.y);
      own[8 * q + 4] += bf_lo(v.z); own[8 * q + 5] += bf_hi(v.z); own[8 * q + 6] += bf_lo(v.w); own[8 * q + 7] += bf_hi(v.w);
    }
    uint32_t v0, v1;
    asm volatile("ld.shared.v2.u32 {%0, %1}, [%2];" : "=r"(v0), "=r"(v1) : "r"(rcv + 8192 + t * 8) : "memory");
    own[32] += bf_lo(v0); own[33] += bf_hi(v0); own[34] += bf_lo(v1); own[35] += bf_hi(v1);
    bar_sync(2 + cx.s, 128);
  }
}

__device__ __forceinline__ uint32_t halo_tag(uint32_t sb, int L) {
  uint32_t e;
  asm volatile("ld.shared.u32 %0, [%1];" : "=r"(e) : "r"(sb + OFF_CONST) : "memory");
  return e * 2 + L + 1;
}

__device__ __forceinline__ void ln_epilogue144(const float (&acc)[72], uint32_t (&out)[36], const Ctx& cx) {
  const float c0 = __shfl_sync(0xffffffffu, acc[33], cx.lane | 3);
  const float c1 = __shfl_sync(0xffffffffu, acc[35], cx.lane | 3);
  const int c = cx.lane & 3;
  const uint32_t mu = cx.sb + OFF_MU + 2 * c * 4, sc = cx.sb + OFF_RS + 2 * c * 4;
#pragma unroll
  for (int j = 0; j < 18; j++) {
    const float2 m = lds64f(mu + j * 32), q = lds64f(sc + j * 32);
    out[2 * j] = pack_bf16(fmaf(-m.x, c0, acc[4 * j + 0]) * q.x, fmaf(-m.y, c0, acc[4 * j + 1]) * q.y);
    out[2 * j + 1] = pack_bf16(fmaf(-m.x, c1, acc[4 * j + 2]) * q.x, fmaf(-m.y, c1, acc[4 * j + 3]) * q.y);
  }
}

__device__ __forceinline__ void ln_gelu72(const float (&acc)[36], uint32_t (&out)[18], const Ctx& cx, int row0, unsigned char* g,
                                          unsigned long long* ll_dst, int L) {
  const float c0 = __shfl_sync(0xffffffffu, acc[33], cx.lane | 3);
  const float c1 = __shfl_sync(0xffffffffu, acc[35], cx.lane | 3);
  const int c = cx.lane & 3;
  const uint32_t mu = cx.sb + OFF_MU + (row0 + 2 * c) * 4, sc = cx.sb + OFF_RR + (row0 + 2 * c) * 4;
  unsigned char* b = g + (2 * cx.w * 9) * 128 + cx.lane * 4;
#pragma unroll
  for (int jj = 0; jj < 9; jj++) {
    const int j = jj == 0 ? 8 : jj - 1;
    const float2 m = lds64f(mu + j * 32), q = lds64f(sc + j * 32);
    out[2 * j] = pack_bf16(gelu_half(fmaf(-m.x, c0, acc[4 * j + 0]) * q.x), gelu_half(fmaf(-m.y, c0, acc[4 * j + 1]) * q.y));
    out[2 * j + 1] = pack_bf16(gelu_half(fmaf(-m.x, c1, acc[4 * j + 2]) * q.x), gelu_half(fmaf(-m.y, c1, acc[4 * j + 3]) * q.y));
    if (g != nullptr) {
      *reinterpret_cast<uint32_t*>(b + j * 128) = out[2 * j];
      *reinterpret_cast<uint32_t*>(b + (9 + j) * 128) = out[2 * j + 1];
    }
    if (jj == 1 && ll_dst != nullptr) {
      const int d = shift_of(cx.r);
      const uint32_t tag = halo_tag(cx.sb, L);
      if (d > 0) {
        for (int x = 0; x < d; x++) {
          const int i = cx.nB - d + x;
          if (c == ((i - 64) >> 1))
            ll_store(ll_dst + x * 32, (i & 1) ? ((out[16] >> 16) | (out[17] & 0xFFFF0000u)) : ((out[16] & 0xFFFFu) | (out[17] << 16)), tag);
        }
      } else if (c == 0) {
        ll_store(ll_dst, (out[0] & 0xFFFFu) | (out[1] << 16), tag);
        if (d == -2) ll_store(ll_dst + 32, (out[0] >> 16) | (out[1] & 0xFFFF0000u), tag);
      }
    }
  }
}

__device__ __forceinline__ void ln_gelu_store(const float (&acc)[72], unsigned char* g, const Ctx& cx
) {
  const float c0 = __shfl_sync(0xffffffffu, acc[33], cx.lane | 3);
  const float c1 = __shfl_sync(0xffffffffu, acc[35], cx.lane | 3);
  const int c = cx.lane & 3;
  const uint32_t mu = cx.sb + OFF_MU + 2 * c * 4, sc = cx.sb + OFF_RR + 2 * c * 4;
  unsigned char* b = g + (2 * cx.w * 9) * 128 + cx.lane * 4;
#pragma unroll
  for (int j = 0; j < 18; j++) {
    const float2 m = lds64f(mu + j * 32), q = lds64f(sc + j * 32);
    const uint32_t p0 = pack_bf16(gelu_half(fmaf(-m.x, c0, acc[4 * j + 0]) * q.x), gelu_half(fmaf(-m.y, c0, acc[4 * j + 1]) * q.y));
    const uint32_t p1 = pack_bf16(gelu_half(fmaf(-m.x, c1, acc[4 * j + 2]) * q.x), gelu_half(fmaf(-m.y, c1, acc[4 * j + 3]) * q.y));
    *reinterpret_cast<uint32_t*>(b + (j / 9) * HALF_B + (j % 9) * 128) = p0;
    *reinterpret_cast<uint32_t*>(b + (j / 9) * HALF_B + (9 + j % 9) * 128) = p1;
  }
}

template <int NJ>
__device__ __forceinline__ void stage_std(const uint32_t (&p)[NJ * 2], uint32_t base, const Ctx& cx) {
  const int m = cx.lane >> 3, l7 = cx.lane & 7;
  const uint32_t a = base + (8 * (m >> 1) + l7) * 128 + (((2 * cx.w + (m & 1)) ^ l7) << 4);
#pragma unroll
  for (int t = 0; t < NJ / 2; t++) stsm4t(a + t * 2048, p[4 * t], p[4 * t + 1], p[4 * t + 2], p[4 * t + 3]);
  if (NJ & 1) {
    const uint32_t a2 = base + l7 * 128 + (((2 * cx.w + (m & 1)) ^ l7) << 4);
    stsm2t(a2 + (NJ / 2) * 2048, p[2 * (NJ - 1)], p[2 * (NJ - 1) + 1]);
  }
}

__device__ __forceinline__ uint32_t par_addr(uint32_t tile, int pstr, int e, int unit) {
  const int par = e & 1, rho = e >> 1;
  return tile + par * pstr + rho * 128 + ((unit ^ ((rho + 4 * par) & 7)) << 4);
}
struct QkvAddr { uint32_t a0, a4, b4, a8; };
template <bool IS_Q>
__device__ __forceinline__ QkvAddr qkv_addr(uint32_t tile, const Ctx& cx) {
  constexpr int PSTR = IS_Q ? QP_B : KP_B, EOFF = IS_Q ? 0 : 14, DUMP_ROW = IS_Q ? 79 : 87;
  const int m = cx.lane >> 3, l7 = cx.lane & 7;
  const int unit = 2 * cx.w + (m & 1), o = 8 * (m >> 1) + l7;
  const uint32_t aA = par_addr(tile, PSTR, o + EOFF, unit);
  const uint32_t aB = par_addr(tile, PSTR, cx.nA + o - 8 + EOFF, unit);
  const uint32_t dump = tile + DUMP_ROW * 128 + (unit << 4);
  QkvAddr q;
  q.a0 = aA;
  q.a4 = o >= 8 ? aB : (64 + o < cx.nA ? aA + 4096 : dump);
  q.b4 = aB;
  q.a8 = (56 + o < cx.nB) ? aB + 4096 : dump;
  return q;
}
__device__ __forceinline__ void stage_qkv(const uint32_t (&p)[36], const QkvAddr& q) {
#pragma unroll
  for (int t = 0; t < 9; t++) {
    const uint32_t a = t < 4 ? q.a0 + 1024 * t : (t == 4 ? q.a4 : (t < 8 ? q.b4 + 1024 * (t - 4) : q.a8));
    stsm4t(a, p[4 * t], p[4 * t + 1], p[4 * t + 2], p[4 * t + 3]);
  }
}

__device__ __forceinline__ void kv_halo_send(const float (&acc)[72], const Ctx& cx, int L, int kv, uint32_t tag) {
  if (cx.cl + 1 >= NCL) return;
  const float c0 = __shfl_sync(0xffffffffu, acc[33], cx.lane | 3), c1 = __shfl_sync(0xffffffffu, acc[35], cx.lane | 3);
  const int c = cx.lane & 3, f = 16 * cx.w + (cx.lane >> 2);
  uint32_t p[6];
#pragma unroll
  for (int j = 15; j < 18; j++) {
    const float2 m = lds64f(cx.sb + OFF_MU + (8 * j + 2 * c) * 4), q = lds64f(cx.sb + OFF_RS + (8 * j + 2 * c) * 4);
    p[2 * (j - 15)] = pack_bf16(fmaf(-m.x, c0, acc[4 * j + 0]) * q.x, fmaf(-m.y, c0, acc[4 * j + 1]) * q.y);
    p[2 * (j - 15) + 1] = pack_bf16(fmaf(-m.x, c1, acc[4 * j + 2]) * q.x, fmaf(-m.y, c1, acc[4 * j + 3]) * q.y);
  }
  unsigned long long* dst = g_llkv + ((size_t)((L * NCL + cx.cl + 1) * CS + cx.r) * 2 + kv) * 512;
  if (c == 3) { ll_store(dst + f * 8 + 0, p[0], tag); ll_store(dst + (f + 8) * 8 + 0, p[1], tag); }
  ll_store(dst + f * 8 + 1 + c, p[2], tag);
  ll_store(dst + (f + 8) * 8 + 1 + c, p[3], tag);
  if (c < 3) { ll_store(dst + f * 8 + 5 + c, p[4], tag); ll_store(dst + (f + 8) * 8 + 5 + c, p[5], tag); }
}

__device__ __forceinline__ void attention(const Ctx& cx, uint32_t qt, uint32_t kt, uint32_t vt, int L) {
  const int warp = cx.s * 4 + cx.w;
  const int hh = warp & 3, p = warp >> 2;
  const int lane = cx.lane, m = lane >> 3, l7 = lane & 7, fr = lane >> 2, c = lane & 3;
  const int n = cx.nA + cx.nB;
  const float sc = 0.25f * 1.4426950408889634f;
  const int key = (l7 + 4 * p) & 7;
  const uint32_t uhi = (uint32_t)(((2 * hh + (m >> 1)) ^ key) << 4), ulo = (uint32_t)(((2 * hh + (m & 1)) ^ key) << 4);
  const uint32_t qa_ = qt + p * QP_B + (8 * (m & 1) + l7) * 128 + uhi;
  const uint32_t ka_ = kt + p * KP_B + (8 * (m >> 1) + l7) * 128 + ulo;
  const uint32_t kb_ = kt + p * KP_B + (16 + l7) * 128 + ulo;
  const uint32_t va_ = vt + p * KP_B + (8 * (m & 1) + l7) * 128 + uhi;
  const uint32_t vb_ = vt + p * KP_B + (16 + l7) * 128 + ulo;
  const uint32_t oslot = cx.sb + cx.r * SLOT_B;
  const float NINF = -INFINITY;
  const float ge0 = (2 * c >= fr) ? 0.f : NINF, ge1 = (2 * c + 1 >= fr) ? 0.f : NINF;
  const float lt0 = (2 * c >= fr) ? NINF : 0.f, lt1 = (2 * c + 1 >= fr) ? NINF : 0.f;
  const uint32_t ones = 0x3F803F80u;
  uint32_t pp[5][4];
  {
    float x[5][8];
#pragma unroll
    for (int blk = 0; blk < 5; blk++) {
      uint32_t qa[4], kf[6];
      ldsm4(qa_ + blk * 2048, qa[0], qa[1], qa[2], qa[3]);
      ldsm4(ka_ + blk * 2048, kf[0], kf[1], kf[2], kf[3]);
      ldsm2(kb_ + blk * 2048, kf[4], kf[5]);
      float s[3][4];
#pragma unroll
      for (int t = 0; t < 3; t++) {
        s[t][0] = s[t][1] = s[t][2] = s[t][3] = 0.f;
        mma16816(s[t], qa[0], qa[1], qa[2], qa[3], kf[2 * t], kf[2 * t + 1]);
      }
      float b0 = ge0, b1 = ge1;
      if (blk == 0 && cx.tokA == 0) {
        b0 = NINF;
        b1 = (c == 3) ? 0.f : NINF;
      }
      x[blk][0] = fmaf(s[0][0], sc, b0); x[blk][1] = fmaf(s[0][1], sc, b1);
      x[blk][2] = fmaf(s[1][0], sc, lt0); x[blk][3] = fmaf(s[1][1], sc, lt1);
      x[blk][4] = fmaf(s[1][2], sc, ge0); x[blk][5] = fmaf(s[1][3], sc, ge1);
      x[blk][6] = fmaf(s[2][2], sc, lt0); x[blk][7] = fmaf(s[2][3], sc, lt1);
    }
    float mx[5], my[5];
#pragma unroll
    for (int blk = 0; blk < 5; blk++) {
      mx[blk] = fmaxf(fmaxf(x[blk][0], x[blk][1]), fmaxf(x[blk][2], x[blk][3]));
      my[blk] = fmaxf(fmaxf(x[blk][4], x[blk][5]), fmaxf(x[blk][6], x[blk][7]));
    }
#pragma unroll
    for (int d = 1; d <= 2; d++) {
#pragma unroll
      for (int blk = 0; blk < 5; blk++) {
        mx[blk] = fmaxf(mx[blk], __shfl_xor_sync(0xffffffffu, mx[blk], d));
        my[blk] = fmaxf(my[blk], __shfl_xor_sync(0xffffffffu, my[blk], d));
      }
    }
#pragma unroll
    for (int blk = 0; blk < 5; blk++) {
      pp[blk][0] = pack_bf16(ex2(x[blk][0] - mx[blk]), ex2(x[blk][1] - mx[blk]));
      pp[blk][1] = pack_bf16(ex2(x[blk][2] - mx[blk]), ex2(x[blk][3] - mx[blk]));
      pp[blk][2] = pack_bf16(ex2(x[blk][4] - my[blk]), ex2(x[blk][5] - my[blk]));
      pp[blk][3] = pack_bf16(ex2(x[blk][6] - my[blk]), ex2(x[blk][7] - my[blk]));
    }
  }
  uint32_t ro[5][4];
#pragma unroll
  for (int blk = 0; blk < 5; blk++) {
    uint32_t vf[6];
    ldsm4t(va_ + blk * 2048, vf[0], vf[1], vf[2], vf[3]);
    ldsm2t(vb_ + blk * 2048, vf[4], vf[5]);
    float o0[4] = {0.f, 0.f, 0.f, 0.f}, o1[4] = {0.f, 0.f, 0.f, 0.f}, sm[4] = {0.f, 0.f, 0.f, 0.f};
    mma16816(o0, pp[blk][0], 0u, pp[blk][1], pp[blk][2], vf[0], vf[1]);
    mma16816(o1, pp[blk][0], 0u, pp[blk][1], pp[blk][2], vf[2], vf[3]);
    mma16816(sm, pp[blk][0], 0u, pp[blk][1], pp[blk][2], ones, ones);
    mma1688(o0, 0u, pp[blk][3], vf[4]);
    mma1688(o1, 0u, pp[blk][3], vf[5]);
    mma1688(sm, 0u, pp[blk][3], ones);
    float i0, i1;
    asm("rcp.approx.ftz.f32 %0, %1;" : "=f"(i0) : "f"(sm[0]));
    asm("rcp.approx.ftz.f32 %0, %1;" : "=f"(i1) : "f"(sm[2]));
    ro[blk][0] = pack_bf16(o0[0] * i0, o0[1] * i0); ro[blk][1] = pack_bf16(o0[2] * i1, o0[3] * i1);
    ro[blk][2] = pack_bf16(o1[0] * i0, o1[1] * i0); ro[blk][3] = pack_bf16(o1[2] * i1, o1[3] * i1);
  }
#pragma unroll
  for (int blk = 0; blk < 5; blk++) {
    const int u = 2 * (16 * blk + 8 * (m & 1) + l7) + p;
    const int row = (u >= n) ? 70 : (u < cx.nA ? u : 72 + (u - cx.nA));
    stsm4(oslot + row * 128 + (((2 * hh + (m >> 1)) ^ (row & 7)) << 4), ro[blk][0], ro[blk][1], ro[blk][2], ro[blk][3]);
  }
}

__device__ __forceinline__ void stats_partial(const Ctx& cx) {
  const int m = cx.lane >> 3, l7 = cx.lane & 7, fr = cx.lane >> 2, c = cx.lane & 3;
  const uint32_t half = cx.sb + cx.r * SLOT_B + cx.s * HALF_B;
  const uint32_t ones = 0x3F803F80u;
  float g0[2][4], g1[4] = {0.f, 0.f, 0.f, 0.f}, sm[2][4];
#pragma unroll
  for (int i = 0; i < 4; i++) { g0[0][i] = g0[1][i] = sm[0][i] = sm[1][i] = 0.f; }
  const uint32_t rowa = half + (16 * cx.w + 8 * (m & 1) + l7) * 128, rowb = half + (64 + 8 * (m & 1) + l7) * 128;
#pragma unroll
  for (int kk = 0; kk < 4; kk++) {
    uint32_t a0, a1, a2, a3, b0, b1, b2, b3;
    const uint32_t u = ((2 * kk + (m >> 1)) ^ l7) << 4;
    ldsm4(rowa + u, a0, a1, a2, a3);
    ldsm4(rowb + u, b0, b1, b2, b3);
    mma16816(g0[0], a0, a1, a2, a3, a0, a2);
    mma16816(g1, a0, a1, a2, a3, a1, a3);
    mma16816(sm[0], a0, a1, a2, a3, ones, ones);
    mma16816(g0[1], b0, b1, b2, b3, b0, b2);
    mma16816(sm[1], b0, b1, b2, b3, ones, ones);
  }
  if (c == (fr >> 1)) {
    const uint32_t dst = cx.sb + OFF_SP + (cx.r * 144 + 72 * cx.s + fr) * 8;
    sts64f(dst + 16 * cx.w * 8, sm[0][0], (fr & 1) ? g0[0][1] : g0[0][0]);
    sts64f(dst + (16 * cx.w + 8) * 8, sm[0][2], (fr & 1) ? g1[3] : g1[2]);
    if (cx.w == 0) sts64f(dst + 64 * 8, sm[1][0], (fr & 1) ? g0[1][1] : g0[1][0]);
  }
  __syncwarp();
}

__device__ __forceinline__ void consumer(const Ctx& cx0, const Params& P) {
  const int s = cx0.s;
  float res[36];
#pragma unroll
  for (int i = 0; i < 36; i++) res[i] = 0.f;

#pragma unroll 1
  for (int it = -1; it < 12; it++) {
    const int L = it >= 6 ? 1 : 0, step = it - 6 * L;
    const int f0 = 7 * L, g0 = 108 * L, q0 = 3 * L;
    const Ctx cx = fresh(cx0);
    const uint32_t sb = cx.sb;
    const int r = cx.r, lane = cx.lane, w = cx.w;
    const uint32_t own = sb + r * SLOT_B;
    const uint32_t own_half = own + s * HALF_B;
    unsigned char* const g3 = g_h3 + (size_t)(cx.cl * CS + r) * 4 * SLOT_B;

    if (it < 0) {

      mbar_wait(sb + B_FULL + 8 * r, 0);

      const int m = lane >> 3, l7 = lane & 7;
      const uint32_t a = own_half + (8 * (m >> 1) + l7) * 128 + (((2 * w + (m & 1)) ^ l7) << 4);
#pragma unroll
      for (int t = 0; t < 4; t++) {
        uint32_t q0_, q1, q2, q3;
        ldsm4t(a + t * 2048, q0_, q1, q2, q3);
        res[8 * t + 0] = bf_lo(q0_); res[8 * t + 1] = bf_hi(q0_); res[8 * t + 2] = bf_lo(q1); res[8 * t + 3] = bf_hi(q1);
        res[8 * t + 4] = bf_lo(q2); res[8 * t + 5] = bf_hi(q2); res[8 * t + 6] = bf_lo(q3); res[8 * t + 7] = bf_hi(q3);
      }
      uint32_t q0_, q1;
      ldsm2t(own_half + l7 * 128 + (((2 * w + (m & 1)) ^ l7) << 4) + 4 * 2048, q0_, q1);
      res[32] = bf_lo(q0_); res[33] = bf_hi(q0_); res[34] = bf_lo(q1); res[35] = bf_hi(q1);
    } else {
      if (step == 0 || step == 4) {
        const bool mlp = step == 4;
        uint32_t pa[36], p[36];
#pragma unroll
        for (int i = 0; i < 36; i++) { pa[i] = 0; p[i] = 0; }
        int sub = 0;
        const uint32_t area = sb + (r < 4 ? 4 : 0) * SLOT_B;
        const uint32_t qt = area, kt = area + 2 * QP_B, vt = kt + 2 * KP_B;
        QkvAddr akv = qkv_addr<false>(s ? vt : kt, cx), aq = qkv_addr<true>(qt, cx);
        asm volatile("" : "+r"(akv.a0), "+r"(akv.a4), "+r"(akv.b4), "+r"(akv.a8), "+r"(aq.a0), "+r"(aq.a4), "+r"(aq.b4), "+r"(aq.a8));
#pragma unroll 1
        while (true) {
          float acc[72];
          mma_tile<144>(acc, cx, 0, g0 + (mlp ? 48 : 0) + (sub == 0 ? 8 * s : 16), f0 & 1, 2, sub == 0, 1,
                        sub == 0 ? 8 * s : 9, sub == 0 ? 8 + s : 0);

          if (mlp && sub == 1) staged_arrive(sb + B_STAGED, lane);
          if (!mlp && sub == 1) bar_sync(1, 256);
          if (sub == 0) mbar_wait(sb + B_SREADY, (q0 + (mlp ? 2 : 0)) & 1);

          if (mlp) {
            ln_gelu_store(acc, g3 + (sub == 0 ? s : 2) * SLOT_B, cx);
            if (sub == 0) global_arrive(sb + B_STAGED2, lane);
          } else {
            if (sub == 0) kv_halo_send(acc, cx, L, s, halo_tag(sb, L));
            ln_epilogue144(acc, p, cx);
          }

          if (sub == 1) break;
          if (!mlp) {
#pragma unroll
            for (int i = 0; i < 36; i++) pa[i] = p[i];
          }
          if (s == 1) break;
          sub = 1;
        }

        if (!mlp) {
          if (s == 0) {
            stage_qkv(pa, akv);
            stage_qkv(p, aq);
          } else {
          const uint32_t tag = halo_tag(sb, L);
          uint32_t hv[8];
          const int t = w * 32 + lane;
          if (cx.cl > 0) {
            const unsigned long long* src = g_llkv + (size_t)((L * NCL + cx.cl) * CS + r) * 1024 + t;
            uint32_t spin = 0;
            while (true) {
              bool ok = true;
#pragma unroll
              for (int i = 0; i < 8; i++) {
                const unsigned long long v = ll_load(src + i * 128);
                hv[i] = (uint32_t)v;
                ok = ok && ((uint32_t)(v >> 32) == tag);
              }
              if (ok) break;
              if (++spin > SPIN_LIMIT) __trap();
              __nanosleep(20);
            }
          }
          const int hprev = 2 * cx.cl - 1;
          const int nBp = ((hprev + 1) * SEQ) / (2 * NCL) - (hprev * SEQ) / (2 * NCL);
          const int u0 = 54 + 2 * (t & 7) - nBp, f = t >> 3;
          const bool v0 = cx.cl > 0 && u0 >= -14 && u0 < 0, v1 = cx.cl > 0 && u0 + 1 >= -14 && u0 + 1 < 0;
          const int e0 = (u0 + 14) & 15, e1 = (u0 + 15) & 15;
          const uint32_t r0 = kt + (e0 & 1) * KP_B + (e0 >> 1) * 128 + (f & 7) * 2, r1 = kt + (e1 & 1) * KP_B + (e1 >> 1) * 128 + (f & 7) * 2;
          const int k0 = ((e0 >> 1) + 4 * (e0 & 1)) & 7, k1 = ((e1 >> 1) + 4 * (e1 & 1)) & 7;
          __syncwarp();

          bar_sync(1, 256);
          stage_qkv(pa, akv);
#pragma unroll
          for (int i = 0; i < 8; i++) {
            const int unit = 2 * (i & 3) + (f >> 3);
            if (v0) sts16(r0 + (i >> 2) * 2 * KP_B + ((unit ^ k0) << 4), hv[i] & 0xFFFFu);
            if (v1) sts16(r1 + (i >> 2) * 2 * KP_B + ((unit ^ k1) << 4), hv[i] >> 16);
          }
        }

          bar_sync(1, 256);

          attention(cx, qt, kt, vt, L);

          staged_arrive(sb + B_STAGED, lane);

          continue;
        }
        if (s == 0) {
          continue;
        }
      }
      float acc[36];
      const int hf = (step == 4) ? (r & 1) : s;
      uint32_t sha = 0, sh0 = 0, sh4 = 0;
      unsigned long long* ll_dst = nullptr;
      if (step == 2) {
        const int d = shift_of(r);
        const int m = lane >> 3, l7 = lane & 7;
        const int unit = 2 * w + (m & 1), o = 8 * (m >> 1) + l7;
        const int ns = s ? cx.nB : cx.nA;
        const int row = 72 * s + o + d;
        sha = own + row * 128 + ((unit ^ (row & 7)) << 4);
        const int row0 = (o + d >= 0) ? row : (s ? cx.nA + o + d : 70);
        sh0 = own + row0 * 128 + ((unit ^ (row0 & 7)) << 4);
        const int i4 = 64 + l7, id = i4 + d;
        const int row4 = (i4 >= ns) ? 70 : (id < ns ? 72 * s + id : (s == 0 ? 72 + id - ns : 70));
        sh4 = own + row4 * 128 + ((unit ^ (row4 & 7)) << 4);
        if (d > 0 && s == 1 && cx.cl + 1 < NCL) ll_dst = g_llh + (size_t)((L * NCL + cx.cl + 1) * CS + r) * 64 + 8 * w + (lane >> 2);
        if (d < 0 && s == 0 && cx.cl > 0) ll_dst = g_llh + (size_t)((L * NCL + cx.cl - 1) * CS + r) * 64 + 8 * w + (lane >> 2);
        asm volatile("" : "+r"(sha), "+r"(sh0), "+r"(sh4), "+l"(ll_dst));
      }
      uint32_t sta;
      {
        const int m = lane >> 3, l7 = lane & 7;
        sta = own_half + (8 * (m >> 1) + l7) * 128 + (((2 * w + (m & 1)) ^ l7) << 4);
        asm volatile("" : "+r"(sta));
      }
      if (step == 3) {
        const uint32_t row4 = (72 * s + 2 * (lane & 3)) * 4;
        const uint32_t mu = sb + OFF_MU + row4, sc = sb + OFF_RS + row4;
#pragma unroll
        for (int j = 0; j < 9; j++) {
          const float2 m = lds64f(mu + j * 32), q = lds64f(sc + j * 32);
          acc[4 * j + 0] = (res[4 * j + 0] - m.x) * q.x;
          acc[4 * j + 1] = (res[4 * j + 1] - m.y) * q.y;
          acc[4 * j + 2] = (res[4 * j + 2] - m.x) * q.x;
          acc[4 * j + 3] = (res[4 * j + 3] - m.y) * q.y;
        }
      } else if (step == 1 || step == 5) {
#pragma unroll
        for (int i = 0; i < 36; i++) acc[i] = res[i];
      } else {
#pragma unroll
        for (int i = 0; i < 36; i++) acc[i] = 0.f;
      }
      if (step == 5) {
        mma_w4(acc, cx, g0 + 80, f0 + 5, L);
      } else {
        if (step == 3) mbar_wait(sb + (s ? B_HALO2 : B_HALO), L & 1);
        mma_tile<72>(acc, cx, hf * HALF_B, g0 + (step == 4 ? 72 : 16 + 8 * step), (f0 + step) & 1, step == 4 ? 2 : 1, step != 4,
                     1, 0, 0);
      }

      if (step == 4) staged_arrive(sb + B_STAGED, lane);
      if (step == 2) bar_arrive(12 + s, 256);
      if (step == 2 || step == 4) {
        if (step == 2) mbar_wait(sb + B_SREADY, (q0 + 1) & 1);

        uint32_t p[18];
        ln_gelu72(acc, p, cx, 72 * hf, step == 4 ? g3 + 3 * SLOT_B : nullptr, ll_dst, L);

        if (step == 2) {
          bar_sync(13 - s, 256);

          stsm4t(sh0, p[0], p[1], p[2], p[3]);
#pragma unroll
          for (int t = 1; t < 4; t++) stsm4t(sha + 2048 * t, p[4 * t], p[4 * t + 1], p[4 * t + 2], p[4 * t + 3]);
          stsm2t(sh4, p[16], p[17]);

          staged_arrive(sb + B_STAGED, lane);
        }

        continue;
      }
      uint32_t p[18];
#pragma unroll
      for (int i = 0; i < 18; i++) p[i] = pack_bf16(acc[2 * i], acc[2 * i + 1]);
      if ((lane & 3) == 3) {
        p[16] = (p[16] & 0xFFFFu) | 0x3F800000u;
        p[17] = (p[17] & 0xFFFFu) | 0x3F800000u;
      }

#pragma unroll
      for (int t = 0; t < 4; t++) stsm4t(sta + t * 2048, p[4 * t], p[4 * t + 1], p[4 * t + 2], p[4 * t + 3]);
      stsm2t(sta + 4 * 2048, p[16], p[17]);

      if (it == 11) {
        bar_sync(2 + s, 128);
        const int ns = s ? cx.nB : cx.nA;
        const int tok0 = cx.tokA + (s ? cx.nA : 0);
        for (int idx = w * 32 + lane; idx < ns * 8; idx += 128) {
          const int row = idx >> 3, u = idx & 7;
          const uint4 v = lds128u(own_half + row * 128 + ((u ^ (row & 7)) << 4));
          *reinterpret_cast<uint4*>(P.out + (size_t)(tok0 + row) * DM + 64 * r + 8 * u) = v;
        }

        break;
      }
      staged_arrive(sb + B_STAGED, lane);
      {
        const float keep = step == 3 ? 1.f : 0.f;
#pragma unroll
        for (int i = 0; i < 36; i++) res[i] = fmaf(res[i], keep, acc[i]);
      }

      bar_sync(2 + s, 128);
    }
    stats_partial(cx);
    bar_arrive(5, 320);
  }
}

struct Ring {
  uint32_t sb;
  int slot;
  uint32_t ph;
  __device__ __forceinline__ void load(const CUtensorMap* m, int x, int y) {
    mbar_wait(sb + B_WEMPTY + 8 * slot, ph ^ 1);
    if (elect_one()) {
      mbar_expect_tx(sb + B_WFULL + 8 * slot, WS_B);
      tma2d(sb + OFF_W + slot * WS_B, m, x, y, sb + B_WFULL + 8 * slot);
    }
    if (++slot == NWS) { slot = 0; ph ^= 1; }
  }
};

__device__ __forceinline__ void producer(uint32_t sb, int r, const Params& P) {
  Ring ring{sb, 0, 0};
  const int g4 = r & 4;
#pragma unroll 1
  for (int t = 0; t < 22; t++) {
    const int k = t >= 11 ? t - 11 : t;
    if (k < 10) {
      const CUtensorMap* m = &P.tqkv + (k < 3 ? 0 : (k < 6 ? k - 2 : 4));
      int col = 64 * r;
      if (k < 2) col += 512 * (k + 1);
      if (k == 7 || k == 8) col += 512 * (k - 6);
      if (k == 9) col = 64 * (24 + (r >> 1));
      int j = r;
#pragma unroll 1
      for (int i = 0; i < 8; i++) {
        ring.load(m, col, 64 * j);
        j = (i + (i >= r ? 1 : 0)) & 7;
      }
    } else {
#pragma unroll 1
      for (int ci = 0; ci < 8; ci++) {
        const int row = 64 * ((ci < 4 ? 0 : 4) + g4 + ci);
        ring.load(&P.tw4, 64 * r, row);
        ring.load(&P.tw4, 64 * (r ^ 4), row);
      }
#pragma unroll 1
      for (int i = 0; i < 12; i++) {
        const int cc = i < 6 ? i : i - 6;
        ring.load(&P.tw4, 64 * (i < 6 ? (r ^ 4) : r), 64 * (cc < 4 ? 16 + g4 + cc : 24 + (g4 >> 1) + (cc - 4)));
      }
    }
  }
}

__device__ __forceinline__ void delay_by_rank(int r, int step) {
  uint32_t t0, t;
  asm volatile("mov.u32 %0, %%clock;" : "=r"(t0));
  do { asm volatile("mov.u32 %0, %%clock;" : "=r"(t)); } while (t - t0 < (uint32_t)(step * r));
}

__device__ __forceinline__ void exchange(uint32_t sb, int r, int cl, int lane, int nB, int tokA, int nA, const Params& P) {
  const uint32_t own = sb + r * SLOT_B, fullr = sb + B_FULL + 8 * r;
  const uint16_t mask_excl = (uint16_t)(0xFF & ~(1 << r));
  const bool lead = elect_one();
  if (lead) {
    tma2d_mc(own, &P.tx, 64 * r, tokA, fullr, 0xFF);
    tma2d_mc(own + HALF_B, &P.tx, 64 * r, tokA + nA, fullr, 0xFF);
  }
  unsigned char* const g3 = g_h3 + (size_t)(cl * CS + r) * 4 * SLOT_B;
  const int a = r & 3;
  const uint16_t gmask = (uint16_t)(0x0F << (r & 4));
#pragma unroll 1
  for (int t = 0; t < 11; t++) {
    const int L = t >= 6 ? 1 : 0, k = t - 6 * L;
    const int fill = 7 * L + (k < 5 ? k + 1 : 7);
    if (k != 4) {
      const uint32_t off = k == 2 ? hfill_off(r) : 0u, len = k == 2 ? hfill_len(r, nB) : (uint32_t)SLOT_B;
      unsigned char* g = g_bounce + (size_t)((cl * 2 + (k & 1)) * CS + r) * SLOT_B + off;
      const uint32_t arm = k == 2 ? hfill_len(lane & 7, nB) : (uint32_t)SLOT_B;
      const uint32_t len0 = HALF_B - off, len1 = len - len0;
      mbar_wait(sb + B_STAGED, t & 1);
      if (lead) {
        fence_async_smem();
        bulk_store(g, own + off, len0);
        bulk_commit();
        bulk_store(g + len0, own + HALF_B, len1);
        bulk_commit();
        mbar_arrive(fullr);
      }
      if (lane < CS) {
        if (lane != r) mbar_expect_tx(sb + B_FULL + 8 * lane, arm);
        mbar_arrive_remote(sb + B_SFREE, lane, 2);
      }
      mbar_wait(sb + B_SFREE, (fill - 1) & 1);
      if (lead) {
        asm volatile("cp.async.bulk.wait_group 1;" ::: "memory");
      }
      __syncwarp();
      delay_by_rank(r, MC_DELAY);
      if (lead) {
        bulk_load_mc(own + off, g, len0, fullr, mask_excl);
        bulk_wait_all();
        bulk_load_mc(own + HALF_B, g + len0, len1, fullr, mask_excl);
      }
    } else {
      const uint32_t sl0 = sb + a * SLOT_B, sl1 = sb + (4 + a) * SLOT_B;
      const uint32_t fb0 = sb + B_FULL + 8 * a, fb1 = sb + B_FULL + 8 * (4 + a);
      mbar_wait(sb + B_STAGED2, 0);
      if (lead) { fence_gpu(); fence_async_global(); }
      __syncwarp();
      mbar_wait(sb + B_STAGED, t & 1);
      if (lead) {
        mbar_expect_tx(sb + B_PBAR, 2 * HALF_B);
      }
      if (lane < CS) {
        mbar_expect_tx(sb + B_FULL + 8 * lane, SLOT_B);
        mbar_arrive_remote(sb + B_SFREE, lane, 2);
      }

      mbar_wait(sb + B_SFREE, (fill - 1) & 1);

      delay_by_rank(a, MC_DELAY);
      if (lead) bulk_load_mc(sl0, g3, SLOT_B, fb0, gmask);
      delay_by_rank(4, MC_DELAY);
      if (lead) {
        bulk_load_mc(sl1, g3 + SLOT_B, SLOT_B, fb1, gmask);
      }
      mbar_wait(sb + B_STAGED2, 1);
      if (lead) { fence_gpu(); fence_async_global(); }
      __syncwarp();
      mbar_wait(sb + B_SFREE, fill & 1);
      if (lead) bulk_load_mc(sl0, g3 + 2 * SLOT_B, SLOT_B, fb0, gmask);
      mbar_wait(sb + B_SFREE2, L & 1);
      if (lead) bulk_load_mc(sl1 + (a & 1) * HALF_B, g3 + 3 * SLOT_B, HALF_B, fb1, gmask);
    }
    __syncwarp();
  }
}

__device__ __forceinline__ void stats_round(uint32_t sb, int r, int t64, int round) {
  const uint32_t mine = sb + OFF_SP + r * 1152;
  bar_sync(5, 320);
  if (t64 < CS) {
    fence_async_smem();
    if (t64 == r) mbar_expect_tx(sb + B_SBAR, 7 * 1152);
    else bulk_s2s(mapa(mine, t64), mine, 1152, mapa(sb + B_SBAR, t64));
  }
  __syncwarp();
  mbar_wait(sb + B_SBAR, round & 1);
#pragma unroll 1
  for (int k3 = 0; k3 < 3; k3++) {
    const int row = t64 + 64 * k3;
    if (row < 144) {
      float2 p[8];
#pragma unroll
      for (int k = 0; k < 8; k++) p[k] = lds64f(sb + OFF_SP + (k * 144 + row) * 8);
      const float s1 = ((p[0].x + p[1].x) + (p[2].x + p[3].x)) + ((p[4].x + p[5].x) + (p[6].x + p[7].x));
      const float s2 = ((p[0].y + p[1].y) + (p[2].y + p[3].y)) + ((p[4].y + p[5].y) + (p[6].y + p[7].y));
      const float mean = s1 * (1.f / 512.f);
      const float var = fmaxf(fmaf(-mean, mean, s2 * (1.f / 512.f)), 0.f);
      const float rstd = rsqrtf(var + LN_EPS);
      const float r2 = (round % 3 == 1) ? rsqrtf(var * rstd * rstd + LN_EPS) : 1.f;
      sts32f(sb + OFF_MU + row * 4, mean);
      sts32f(sb + OFF_RS + row * 4, rstd);
      sts32f(sb + OFF_RR + row * 4, 0.5f * rstd * r2);
    }
  }
  __syncwarp();
  if ((t64 & 31) == 0) mbar_arrive(sb + B_SREADY);
}

__device__ __forceinline__ void h_halo_recv(uint32_t sb, int cl, int lane, int nB, uint32_t tag, int L, int side) {
  const unsigned long long* src = g_llh + (size_t)(L * NCL + cl) * CS * 64 + lane + side * 2 * 64;
  const bool have = side == 0 ? (cl > 0) : (cl + 1 < NCL);
  uint32_t hv[6] = {0, 0, 0, 0, 0, 0};
  uint32_t it = 0;
  while (have) {
    bool ok = true;
#pragma unroll
    for (int n = 0; n < 6; n++) {
      const int off = n < 2 ? n * 64 : (4 + ((n - 2) >> 1)) * 64 + ((n - 2) & 1) * 32;
      const unsigned long long q = ll_load(src + off);
      hv[n] = (uint32_t)q;
      ok = ok && ((uint32_t)(q >> 32) == tag);
    }
    if (__all_sync(0xffffffffu, ok)) break;
    if (++it > SPIN_LIMIT) __trap();
  }
  const int wq = lane >> 3, i = lane & 7;
#pragma unroll
  for (int n = 0; n < 6; n++) {
    const int j = (n < 2 ? n : 4 + ((n - 2) >> 1)) + 2 * side, x = n < 2 ? 0 : ((n - 2) & 1);
    const int row = side == 0 ? x : 72 + nB - (n < 2 ? 1 : 2) + x;
    const uint32_t a = sb + j * SLOT_B + row * 128 + i * 2;
    sts16(a + (((2 * wq) ^ (row & 7)) << 4), hv[n] & 0xFFFFu);
    sts16(a + (((2 * wq + 1) ^ (row & 7)) << 4), hv[n] >> 16);
  }
  fence_async_smem();
  __syncwarp();
  if (lane == 0) mbar_arrive(sb + (side ? B_HALO2 : B_HALO));
}

__device__ __forceinline__ void helper_warps(uint32_t sb, int r, int cl, int warp, int lane, int nB) {
  int round = 0;
  uint32_t epoch;
  asm volatile("ld.relaxed.gpu.global.u32 %0, [%1];" : "=r"(epoch) : "l"(g_epoch + cl * CS + r) : "memory");
  if (warp == 11) {
    if (lane == 0) asm volatile("st.shared.u32 [%0], %1;" ::"r"(sb + OFF_CONST), "r"(epoch) : "memory");
    __syncwarp();
  }
#pragma unroll 1
  for (int t = -1; t < 11; t++) {
    const int L = t >= 6 ? 1 : 0, k = t - 6 * L;
    sb = (uint32_t)opaque((int)sb); r = opaque(r); cl = opaque(cl); lane = opaque(lane); nB = opaque(nB);
    const int t64 = (warp - 10) * 32 + lane;
    if (t >= 0) mbar_wait(sb + B_STAGED, t & 1);
    if (k == -1 || k == 1 || k == 3 || k == 5) {
      stats_round(sb, r, t64, round++);
    } else if (k == 2) {
      h_halo_recv(sb, cl, lane, nB, epoch * 2 + L + 1, L, warp - 10);
    } else if (k == 4) {
      if (warp == 11 && lane == 0) {
#pragma unroll 1
        for (int e = 0; e < 8; e++) {
          const uint32_t bar = sb + B_FULL + 8 * e;
          mbar_wait(bar, (7 * L + 5) & 1);
          mbar_expect_tx(bar, e < 4 ? SLOT_B : HALF_B);
        }
      }
      __syncwarp();
      const int ws = warp - 10;
      bar_sync(10 + ws, 160);
      if (lane == 0) {
        fence_async_smem();
        mbar_wait(sb + B_RXF, L & 1);
        const uint32_t snd = sb + (5 - ws + ((r == 5 - ws) ? 2 : 0)) * SLOT_B + ws * HALF_B;
        const uint32_t rcv = sb + (7 - ws - (((r ^ 4) == 5 - ws) ? 2 : 0)) * SLOT_B + ws * HALF_B;
        bulk_s2s(mapa(rcv, r ^ 4), snd, HALF_B, mapa(sb + B_PBAR, r ^ 4));
      }
      __syncwarp();
    }
  }
  if (warp == 11 && lane == 0) g_epoch[cl * CS + r] = epoch + 1;
}

__global__ void __cluster_dims__(CS, 1, 1) __launch_bounds__(384, 1) fused_kernel(const __grid_constant__ Params P) {
  extern __shared__ __align__(1024) unsigned char smem[];
  const uint32_t sb = smem_u32(smem);
  const int tid = threadIdx.x, warp = __shfl_sync(0xffffffffu, tid >> 5, 0), lane = tid & 31;
  uint32_t r, cl;
  asm("mov.u32 %0, %%cluster_ctarank;" : "=r"(r));
  asm("mov.u32 %0, %%clusterid.x;" : "=r"(cl));
  const int t0 = (2 * cl * SEQ) / (2 * NCL), t1 = ((2 * cl + 1) * SEQ) / (2 * NCL), t2 = ((2 * cl + 2) * SEQ) / (2 * NCL);
  if (tid == 288) {
    asm volatile("cp.async.bulk.prefetch.tensor.2d.L2.global.tile [%0, {%1, %2}];" ::"l"(&P.tx), "r"((int)(64 * r)), "r"(t0) : "memory");
    asm volatile("cp.async.bulk.prefetch.tensor.2d.L2.global.tile [%0, {%1, %2}];" ::"l"(&P.tx), "r"((int)(64 * r)), "r"(t1) : "memory");
  }
  if (lane == 0) {
    if (sb & 1023) __trap();
#pragma unroll
    for (int q = 0; q < 3; q++) {
      const int b = 3 * warp + q;
      const uint32_t cnt = b < 17 ? 1u : (b < 26 ? 2u : (b == 26 ? 16u : ((b == 27 || b == 28 || b == 32) ? 8u : ((b == 30 || b == 33) ? 2u : 1u))));
      if (b < 36) mbar_init(sb + B_FULL + 8 * b, cnt);
      if (b < 8) mbar_expect_tx(sb + B_FULL + 8 * b, 2 * 69 * 128);
    }
    asm volatile("fence.mbarrier_init.release.cluster;" ::: "memory");
  }
  {
    const int hs = tid / 24, rem = tid % 24, row = 69 + rem / 8, u = rem % 8;
    const uint32_t val = row == 71 ? 0x3F803F80u : 0u;
    sts128u(sb + hs * HALF_B + row * 128 + u * 16, val, val, val, val);
  }
  __syncthreads();
  asm volatile("barrier.cluster.arrive.relaxed;" ::: "memory");

  if (warp < 8) {
    asm volatile("setmaxnreg.inc.sync.aligned.u32 224;");
    Ctx cx;
    cx.sb = sb; cx.r = r; cx.cl = cl; cx.s = warp >> 2; cx.w = warp & 3; cx.lane = lane;
    cx.nA = t1 - t0; cx.nB = t2 - t1; cx.tokA = t0; cx.el = opaque((tid & 127) == 0 ? 1 : 0);
    consumer(cx, P);
    __syncwarp();
    cluster_wait();
  } else {
    asm volatile("setmaxnreg.dec.sync.aligned.u32 56;");
    if (warp == 8) {
      producer(sb, r, P);
      __syncwarp();
      cluster_wait();
    } else if (warp == 9) {
      cluster_wait();
      exchange(sb, r, cl, lane, t2 - t1, t0, t1 - t0, P);
    } else {
      helper_warps(sb, r, cl, warp, lane, t2 - t1);
      __syncwarp();
      cluster_wait();
    }
  }
  __syncwarp();
  asm volatile("barrier.cluster.arrive.relaxed;" ::: "memory");
  cluster_wait();
}

typedef CUresult (*EncodeFn)(CUtensorMap*, CUtensorMapDataType, cuuint32_t, void*, const cuuint64_t*, const cuuint64_t*,
                             const cuuint32_t*, const cuuint32_t*, CUtensorMapInterleave, CUtensorMapSwizzle,
                             CUtensorMapL2promotion, CUtensorMapFloatOOBfill);

static void make_map(EncodeFn fn, CUtensorMap* m, const void* ptr, int rows, int cols, int box_rows) {
  cuuint64_t dims[2] = {(cuuint64_t)cols, (cuuint64_t)rows};
  cuuint64_t strides[1] = {(cuuint64_t)cols * 2};
  cuuint32_t box[2] = {64, (cuuint32_t)box_rows};
  cuuint32_t es[2] = {1, 1};
  fn(m, CU_TENSOR_MAP_DATA_TYPE_BFLOAT16, 2, const_cast<void*>(ptr), dims, strides, box, es, CU_TENSOR_MAP_INTERLEAVE_NONE,
     CU_TENSOR_MAP_SWIZZLE_128B, CU_TENSOR_MAP_L2_PROMOTION_L2_256B, CU_TENSOR_MAP_FLOAT_OOB_FILL_NONE);
}

namespace fb {
__device__ float g_x[SEQ * DM], g_xa[SEQ * DM], g_xn[SEQ * DM], g_x1[SEQ * DM];
__device__ __nv_bfloat16 g_a[SEQ * DM], g_b[SEQ * DM], g_big[SEQ * FF];

__global__ void k_load(const __nv_bfloat16* in, float* x) {
  const int i = blockIdx.x * blockDim.x + threadIdx.x;
  x[i] = __bfloat162float(in[i]);
}
__global__ void k_store(const float* x, __nv_bfloat16* out) {
  const int i = blockIdx.x * blockDim.x + threadIdx.x;
  out[i] = __float2bfloat16(x[i]);
}
__global__ void k_ln(const float* x, float* keep, __nv_bfloat16* y, int twice) {
  __shared__ float red[4];
  const int t = threadIdx.x;
  float v[4];
  for (int i = 0; i < 4; i++) v[i] = x[blockIdx.x * DM + t + 128 * i];
  for (int pass = 0; pass <= twice; pass++) {
    float s = v[0] + v[1] + v[2] + v[3];
    for (int o = 16; o > 0; o >>= 1) s += __shfl_xor_sync(0xffffffffu, s, o);
    if ((t & 31) == 0) red[t >> 5] = s;
    __syncthreads();
    const float mean = (red[0] + red[1] + red[2] + red[3]) * (1.f / DM);
    __syncthreads();
    float q = 0.f;
    for (int i = 0; i < 4; i++) { v[i] -= mean; q = fmaf(v[i], v[i], q); }
    for (int o = 16; o > 0; o >>= 1) q += __shfl_xor_sync(0xffffffffu, q, o);
    if ((t & 31) == 0) red[t >> 5] = q;
    __syncthreads();
    const float rstd = 1.f / sqrtf((red[0] + red[1] + red[2] + red[3]) * (1.f / DM) + LN_EPS);
    __syncthreads();
    for (int i = 0; i < 4; i++) v[i] *= rstd;
    if (pass == 0 && keep) for (int i = 0; i < 4; i++) keep[blockIdx.x * DM + t + 128 * i] = v[i];
  }
  for (int i = 0; i < 4; i++) y[blockIdx.x * DM + t + 128 * i] = __float2bfloat16(v[i]);
}
__global__ void k_gemm(const __nv_bfloat16* A, const __nv_bfloat16* B, int K, int N, int mode, __nv_bfloat16* outb,
                       float* outf, const float* add1, const float* add2) {
  using namespace nvcuda;
  __shared__ float st[4][32 * 32];
  const int w = threadIdx.x >> 5, lane = threadIdx.x & 31;
  const int m0 = blockIdx.y * 64 + (w >> 1) * 32, n0 = blockIdx.x * 64 + (w & 1) * 32;
  wmma::fragment<wmma::accumulator, 16, 16, 16, float> c[2][2];
  for (int i = 0; i < 2; i++) for (int j = 0; j < 2; j++) wmma::fill_fragment(c[i][j], 0.f);
  for (int k = 0; k < K; k += 16) {
    wmma::fragment<wmma::matrix_a, 16, 16, 16, __nv_bfloat16, wmma::row_major> a[2];
    wmma::fragment<wmma::matrix_b, 16, 16, 16, __nv_bfloat16, wmma::row_major> b[2];
    for (int i = 0; i < 2; i++) wmma::load_matrix_sync(a[i], A + (size_t)(m0 + 16 * i) * K + k, K);
    for (int j = 0; j < 2; j++) wmma::load_matrix_sync(b[j], B + (size_t)k * N + n0 + 16 * j, N);
    for (int i = 0; i < 2; i++) for (int j = 0; j < 2; j++) wmma::mma_sync(c[i][j], a[i], b[j], c[i][j]);
  }
  for (int i = 0; i < 2; i++) for (int j = 0; j < 2; j++)
    wmma::store_matrix_sync(&st[w][16 * i * 32 + 16 * j], c[i][j], 32, wmma::mem_row_major);
  __syncwarp();
  for (int e = lane; e < 32 * 32; e += 32) {
    const size_t o = (size_t)(m0 + e / 32) * N + n0 + e % 32;
    const float v = st[w][e];
    if (mode == 0) outb[o] = __float2bfloat16(v);
    else if (mode == 1) {
      const float u = 0.7978845608028654f * (v + 0.044715f * v * v * v);
      outb[o] = __float2bfloat16(0.5f * v * (1.f + tanhf(u)));
    } else outf[o] = v + add1[o] + (add2 ? add2[o] : 0.f);
  }
}
__global__ void k_attn(const __nv_bfloat16* qkv, __nv_bfloat16* o) {
  const int i = blockIdx.x * blockDim.x + threadIdx.x, tok = i >> 5, h = i & 31;
  float q[16], lg[8], acc[16], mx = -INFINITY, sum = 0.f;
  for (int d = 0; d < 16; d++) { q[d] = __bfloat162float(qkv[(size_t)tok * 1536 + 16 * h + d]); acc[d] = 0.f; }
  for (int w = 0; w < 8; w++) {
    const int k = tok - 2 * w;
    lg[w] = -INFINITY;
    if (k >= 0) {
      float s = 0.f;
      for (int d = 0; d < 16; d++) s = fmaf(q[d], __bfloat162float(qkv[(size_t)k * 1536 + 512 + 16 * h + d]), s);
      lg[w] = 0.25f * s;
    }
    mx = fmaxf(mx, lg[w]);
  }
  for (int w = 0; w < 8; w++) {
    const int k = tok - 2 * w;
    if (k < 0) continue;
    const float p = __expf(lg[w] - mx);
    sum += p;
    for (int d = 0; d < 16; d++) acc[d] = fmaf(p, __bfloat162float(qkv[(size_t)k * 1536 + 1024 + 16 * h + d]), acc[d]);
  }
  for (int d = 0; d < 16; d++) o[(size_t)tok * DM + 16 * h + d] = __float2bfloat16(acc[d] / sum);
}
__global__ void k_shift(const __nv_bfloat16* h, __nv_bfloat16* y) {
  const int i = blockIdx.x * blockDim.x + threadIdx.x, tok = i / DM, f = i % DM;
  const int src = tok - shift_of(f >> 6);
  y[i] = (src >= 0 && src < SEQ) ? h[(size_t)src * DM + f] : __float2bfloat16(0.f);
}

template <typename T>
static T* sym(const T& s) { void* p = nullptr; cudaGetSymbolAddress(&p, s); return (T*)p; }

static void run(void* const* d_in, void* d_out) {
  cudaStream_t st = cudaStreamPerThread;
  float *x = (float*)sym(g_x), *xa = (float*)sym(g_xa), *xn = (float*)sym(g_xn), *x1 = (float*)sym(g_x1);
  __nv_bfloat16 *a = (__nv_bfloat16*)sym(g_a), *b = (__nv_bfloat16*)sym(g_b), *big = (__nv_bfloat16*)sym(g_big);
  const __nv_bfloat16 *wqkv = (const __nv_bfloat16*)d_in[1], *wo = (const __nv_bfloat16*)d_in[2], *w1 = (const __nv_bfloat16*)d_in[4],
                      *w2 = (const __nv_bfloat16*)d_in[5], *w3 = (const __nv_bfloat16*)d_in[6], *w4 = (const __nv_bfloat16*)d_in[7];
  const int ne = SEQ * DM / 256;
  k_load<<<ne, 256, 0, st>>>((const __nv_bfloat16*)d_in[0], x);
  for (int L = 0; L < 2; L++) {
    k_ln<<<SEQ, 128, 0, st>>>(x, nullptr, a, 0);
    k_gemm<<<dim3(1536 / 64, SEQ / 64), 128, 0, st>>>(a, wqkv, DM, 1536, 0, big, nullptr, nullptr, nullptr);
    k_attn<<<SEQ * 32 / 128, 128, 0, st>>>(big, b);
    k_gemm<<<dim3(DM / 64, SEQ / 64), 128, 0, st>>>(b, wo, DM, DM, 2, nullptr, xa, x, nullptr);
    k_ln<<<SEQ, 128, 0, st>>>(xa, xn, a, 1);
    k_gemm<<<dim3(DM / 64, SEQ / 64), 128, 0, st>>>(a, w1, DM, DM, 1, b, nullptr, nullptr, nullptr);
    k_shift<<<ne, 256, 0, st>>>(b, a);
    k_gemm<<<dim3(DM / 64, SEQ / 64), 128, 0, st>>>(a, w2, DM, DM, 2, nullptr, x1, xn, nullptr);
    k_ln<<<SEQ, 128, 0, st>>>(x1, nullptr, a, 0);
    k_gemm<<<dim3(FF / 64, SEQ / 64), 128, 0, st>>>(a, w3, DM, FF, 1, big, nullptr, nullptr, nullptr);
    k_gemm<<<dim3(DM / 64, SEQ / 64), 128, 0, st>>>(big, w4, FF, DM, 2, nullptr, x, xa, x1);
  }
  k_store<<<ne, 256, 0, st>>>(x, (__nv_bfloat16*)d_out);
}
}
}

extern "C" void kernel_launch(void* const* d_in, const int* in_sizes, int n_in, void* d_out, int out_size) {
  using namespace mk;
  static EncodeFn enc = nullptr;
  static int mode = -1;
  if (mode < 0) {
    void* fn = nullptr;
    cudaDriverEntryPointQueryResult qr;
    cudaGetDriverEntryPoint("cuTensorMapEncodeTiled", &fn, cudaEnableDefault, &qr);
    enc = (EncodeFn)fn;
    int nclusters = 0;
    if (enc && cudaFuncSetAttribute(fused_kernel, cudaFuncAttributeMaxDynamicSharedMemorySize, SMEM_BYTES) == cudaSuccess) {
      cudaLaunchConfig_t cfg = {};
      cfg.gridDim = dim3(NCL * CS); cfg.blockDim = dim3(384); cfg.dynamicSmemBytes = SMEM_BYTES;
      cudaLaunchAttribute at[1];
      at[0].id = cudaLaunchAttributeClusterDimension;
      at[0].val.clusterDim.x = CS; at[0].val.clusterDim.y = 1; at[0].val.clusterDim.z = 1;
      cfg.attrs = at; cfg.numAttrs = 1;
      if (cudaOccupancyMaxActiveClusters(&nclusters, fused_kernel, &cfg) != cudaSuccess) nclusters = 0;
    }
    (void)cudaGetLastError();
    mode = nclusters >= NCL ? 1 : 0;
  }
  if (mode == 0) { fb::run(d_in, d_out); return; }
  Params P;
  make_map(enc, &P.tx, d_in[0], SEQ, DM, 69);
  make_map(enc, &P.tqkv, d_in[1], DM, 3 * DM, 64);
  make_map(enc, &P.two, d_in[2], DM, DM, 64);
  make_map(enc, &P.tw1, d_in[4], DM, DM, 64);
  make_map(enc, &P.tw2, d_in[5], DM, DM, 64);
  make_map(enc, &P.tw3, d_in[6], DM, FF, 64);
  make_map(enc, &P.tw4, d_in[7], FF, DM, 64);
  P.out = (__nv_bfloat16*)d_out;
  fused_kernel<<<NCL * CS, 384, SMEM_BYTES, cudaStreamPerThread>>>(P);
}
```
